```python
import torch

def _softmax(x, axis=-1):
    return torch.softmax(x, dim=axis)
def _gelu(x):
    return torch.nn.functional.gelu(x, approximate="tanh")
def _silu(x):
    return torch.nn.functional.silu(x)
def _sigmoid(x):
    return torch.sigmoid(x)
def _layernorm(x, axis=-1, eps=1e-5):
    m = x.mean(dim=axis, keepdim=True)
    v = x.var(dim=axis, keepdim=True, unbiased=False)
    return (x - m) / torch.sqrt(v + eps)
def _scatter_add(tgt, idx, src, axis=0):
    return tgt.clone().index_add_(axis, idx, src)
def _segment_sum(src, seg, n):
    out = torch.zeros((n,) + src.shape[1:], dtype=src.dtype)
    return out.index_add_(0, seg, src)
def _pad(x, pw):
    flat = tuple(v for pair in reversed(pw) for v in pair)
    return torch.nn.functional.pad(x, flat)

kernel_name = 'recurrent_scan__ssm_conv_s4d__moe_arch_mod__prompt'

def setup_inputs():

    _w = (lambda a: (lambda t: t.to(torch.bfloat16) if t.is_floating_point() else t)(torch.as_tensor(a)))
    def _A_setup():
        Bsz, L, D, N = 1, 2048, 512, 128
        return {
            "u": _w((lambda *s: torch.randn(*s, dtype=torch.bfloat16) * 0.05)(Bsz, L, D)),
            "log_A_real": _w((lambda *s: torch.randn(*s, dtype=torch.bfloat16) * 3.2)(D, N) * 0.5),
            "A_imag": _w((lambda *s: torch.randn(*s, dtype=torch.bfloat16) * 0.05)(D, N) * 3.14),
            "C_real": _w((lambda *s: torch.randn(*s, dtype=torch.bfloat16) * 0.1)(D, N) / N ** 0.5),
            "C_imag": _w((lambda *s: torch.randn(*s, dtype=torch.bfloat16) * 0.1)(D, N) / N ** 0.5),
            "log_dt": _w((lambda *s: torch.randn(*s, dtype=torch.bfloat16) * 0.05)(D) * 0.5 - 4.0),
            "D_skip": _w((lambda *s: torch.randn(*s, dtype=torch.bfloat16) * 0.05)(D)),
        }
    _A_in = _A_setup()

    def _B_setup():
        B, S, D, F, C = 1, 2048, 512, 1376, 1
        return {
            "x": _w((lambda *s: torch.randn(*s, dtype=torch.bfloat16) * 0.05)(B, S, D)),
            "w_r": _w((lambda *s: torch.randn(*s, dtype=torch.bfloat16) * 3.2)(D)),
            "w_gate": _w((lambda *s: torch.randn(*s, dtype=torch.bfloat16) * 0.1)(D, F)),
            "w_up": _w((lambda *s: torch.randn(*s, dtype=torch.bfloat16) * 0.1)(D, F)),
            "w_down": _w((lambda *s: torch.randn(*s, dtype=torch.bfloat16) * 0.1)(F, D)),
        }
    _B_in = _B_setup()

    return {
        "A_u": _A_in["u"],
        "A_log_A_real": _A_in["log_A_real"],
        "A_A_imag": _A_in["A_imag"],
        "A_C_real": _A_in["C_real"],
        "A_C_imag": _A_in["C_imag"],
        "A_log_dt": _A_in["log_dt"],
        "A_D_skip": _A_in["D_skip"],
        "B_x": _B_in["x"],
        "B_w_r": _B_in["w_r"],
        "B_w_gate": _B_in["w_gate"],
        "B_w_up": _B_in["w_up"],
        "B_w_down": _B_in["w_down"],
    }

def reference(A_u, A_log_A_real, A_A_imag, A_C_real, A_C_imag, A_log_dt, A_D_skip, B_x, B_w_r, B_w_gate, B_w_up, B_w_down):
    def _A_ref(u, log_A_real, A_imag, C_real, C_imag, log_dt, D_skip):
        L = u.shape[1]
        dt = torch.exp(log_dt)
        A = -torch.exp(log_A_real) + 1j * A_imag
        C = (C_real + 1j * C_imag) * dt[:, None]
        pos = (lambda x, dt: x.to(dt))(torch.arange(L), log_dt.dtype)
        P = torch.exp((A * dt[:, None])[:, :, None] * pos[None, None, :])
        K = 2.0 * torch.einsum("dn,dnl->dl", C, P).real
        L2 = 2 * L
        u_t = (lambda x, *d: x.permute(*d))(u, 0, 2, 1)
        Kf = (lambda x, *a, **k: torch.fft.rfft(x.float(), *a, **k))(K, L2)
        Uf = (lambda x, *a, **k: torch.fft.rfft(x.float(), *a, **k))(u_t, L2)
        y = (lambda x, *a, **k: torch.fft.irfft(x, *a, **k).to(torch.bfloat16))(Uf * Kf[None, :, :], L2)[:, :, :L]
        y = (lambda x, *d: x.permute(*d))(y, 0, 2, 1)
        return y + u * D_skip[None, None, :]

    def _B_ref(x, w_r, w_gate, w_up, w_down):
        B, S, D = x.shape
        C = 1
        r = x @ w_r
        idx = torch.argsort(-r, axis=-1)[:, :C]
        idx_e = (lambda x, n, axis: torch.repeat_interleave(x, n, dim=axis))(idx.reshape(B, C, 1), D, axis=2)
        x_sel = (lambda x, i, axis: torch.take_along_dim(x, i, dim=axis))(x, idx_e, axis=1)
        g = _silu(x_sel @ w_gate)
        u = x_sel @ w_up
        y = (g * u) @ w_down
        r_sel = _sigmoid((lambda x, i, axis: torch.take_along_dim(x, i, dim=axis))(r, idx, axis=1))
        y = y * r_sel.reshape(B, C, 1)
        b_off = (torch.arange(B) * S).reshape(B, 1)
        flat_idx = (idx + b_off).reshape(B * C)
        zero = (x * 0.0).reshape(B * S, D)
        upd = _scatter_add(zero, flat_idx, y.reshape(B * C, D), axis=0)
        return x + upd.reshape(B, S, D)

    x = A_u
    xn = _layernorm(x, axis=-1)
    s = _A_ref(xn, A_log_A_real, A_A_imag, A_C_real, A_C_imag, A_log_dt, A_D_skip)
    g = _silu(_B_ref(xn, B_w_r, B_w_gate, B_w_up, B_w_down))
    return x + s * g
```

```cpp
#include <cuda_runtime.h>
#include <cuda.h>
#include <cuda_bf16.h>
#include <cuda_fp16.h>
#include <stdint.h>
#include <stdio.h>
#include <type_traits>

namespace {

constexpr int NCTA = 128;
constexpr int NFFN = 86;
#define STAGGER 40
#define ROLEMAP 0x43210
#define WJ 6
#define SBASE 750
#define PUSHLAG 0
#define KPAUSE 1
#define WMODE 0
#define MSKEW 0
#define FSLEEP 20
#define PGATE rk
#define KREL 1
#define GDELAY 600
#define RLATE 0
#define ALT 1
#define GPOS 2
#define RJ 7
#define JSWAP 4
#define CSTART 1400
#define CSTEP 20
#define PSTART 1500
#define PSTEP 160
#define WSTART 1500

constexpr int OFF_XS = 0;
constexpr int OFF_WG = 16384;
constexpr int OFF_WU = 32768;
constexpr int OFF_WD = 49152;
constexpr int OFF_Y = 65536;
constexpr int UPL = 2240, UCH = 2 * UPL;
constexpr int OFF_U = OFF_Y + 16384;
constexpr int OFF_CH = OFF_U + 4 * UCH;
constexpr int PL = 6224;
constexpr int C_A3 = 16, C_W5 = C_A3 + 1552, C_W7 = C_W5 + 1552, C_W9 = C_W7 + 1040, C_Z5 = C_W9 + 1040;
constexpr int C_WT = 2 * PL + 64;
constexpr int C_PG = C_WT + 2336 + 64;
constexpr int RPL = 1600;
constexpr int C_RG = C_PG + 1088, C_BP = C_RG + 8 * RPL;
constexpr int CHS = C_BP + 2 * RPL;
constexpr int KG_STRIDE = 528;
constexpr int C_KP = CHS - 6144;
static_assert(32 * KG_STRIDE <= C_KP && CHS % 16 == 0, "map");
constexpr int OFF_WR = OFF_CH + 4 * CHS;
constexpr int OFF_XN = OFF_WR;
constexpr int OFF_FP = OFF_XN + 1024;
constexpr int OFF_ST = OFF_FP + 512;
constexpr int OFF_RK = OFF_ST + 128;
constexpr int OFF_FLG = OFF_RK + 64;
constexpr int OFF_BAR = OFF_FLG + 96;
constexpr int BAR_U = 0, BAR_X = 16, BAR_Y = 24, BAR_W = 32, BAR_R = 36, NBAR = 40;
constexpr int SMEM_BYTES = OFF_BAR + 8 * NBAR;
static_assert(SMEM_BYTES <= 232448, "smem");
constexpr int NREP = 4;

constexpr int SPIN_LIMIT = 1 << 16;

struct Scratch {
    uint4 stats[NREP * NCTA * 8];
    long long acc[8 * 64 * 16];
    uint32_t route[NCTA * 8];
    uint32_t epoch[NCTA * 8];
};
__device__ __align__(128) Scratch g_scratch;
#define TS(i)
#define TS_INIT
#define TS_DUMP
#define TS_SMEM 0
#define GT_SMEM 0

__device__ __forceinline__ uint32_t mapa(uint32_t a, uint32_t r) {
    uint32_t o; asm("mapa.shared::cluster.u32 %0, %1, %2;" : "=r"(o) : "r"(a), "r"(r)); return o;
}
__device__ __forceinline__ bool mbar_try(uint32_t a) {
    uint32_t p;
    asm volatile("{.reg .pred p; mbarrier.test_wait.parity.shared::cta.b64 p, [%1], 0; selp.u32 %0, 1, 0, p;}"
                 : "=r"(p) : "r"(a) : "memory");
    return p;
}
__device__ __forceinline__ void mbar_wait(uint32_t a) {
    asm volatile("{.reg .pred p; .reg .u32 n; mov.u32 n, 4096;\n"
                 "W%=: mbarrier.try_wait.parity.shared::cta.b64 p, [%0], 0;\n"
                 "sub.u32 n, n, 1; setp.eq.or.u32 p, n, 0, p; @!p bra W%=;}" :: "r"(a) : "memory");
}
__device__ __forceinline__ void mbar_wait_long(uint32_t a) {
    asm volatile("{.reg .pred p; .reg .u32 n; mov.u32 n, 4096;\n"
                 "W%=: mbarrier.try_wait.parity.shared::cta.b64 p, [%0], 0, 4000;\n"
                 "sub.u32 n, n, 1; setp.eq.or.u32 p, n, 0, p; @!p bra W%=;}" :: "r"(a) : "memory");
}
__device__ __forceinline__ void mbar_init_tx(uint32_t a, uint32_t tx, uint32_t cnt = 1) {
    asm volatile("mbarrier.init.shared::cta.b64 [%0], %1;" :: "r"(a), "r"(cnt) : "memory");
    asm volatile("mbarrier.arrive.expect_tx.shared::cta.b64 _, [%0], %1;" :: "r"(a), "r"(tx) : "memory");
}
__device__ __forceinline__ bool elect_one() {
    uint32_t p; asm volatile("{.reg .pred p; elect.sync _|p, 0xffffffff; selp.u32 %0, 1, 0, p;}" : "=r"(p)); return p;
}
__device__ __forceinline__ uint32_t ld_flag(uint32_t a) {
    uint32_t v; asm volatile("ld.volatile.shared.u32 %0, [%1];" : "=r"(v) : "r"(a) : "memory"); return v;
}
__device__ __forceinline__ void st_flag(uint32_t a, uint32_t v) {
    asm volatile("st.volatile.shared.u32 [%0], %1;" :: "r"(a), "r"(v) : "memory");
}
__device__ __forceinline__ void flag_wait(uint32_t a, int v) {
#pragma unroll 1
    for (int n = 0; n < (SPIN_LIMIT << 6) && (int)ld_flag(a) < v; n++) __nanosleep(20);
}
__device__ __forceinline__ void bar_sync(int id, int n) { asm volatile("bar.sync %0, %1;" :: "r"(id), "r"(n) : "memory"); }
__device__ __forceinline__ void bar_arrive(int id, int n) { asm volatile("bar.arrive %0, %1;" :: "r"(id), "r"(n) : "memory"); }
template <int OFF = 0>
__device__ __forceinline__ uint4 ld_relaxed4(const void* p) {
    uint4 v;
    asm volatile("ld.relaxed.gpu.global.v4.u32 {%0,%1,%2,%3}, [%4+%5];" : "=r"(v.x), "=r"(v.y), "=r"(v.z), "=r"(v.w) : "l"(p), "n"(OFF) : "memory");
    return v;
}
__device__ __forceinline__ uint2 ld_relaxed2(const void* p) {
    uint2 v; asm volatile("ld.relaxed.gpu.global.v2.u32 {%0,%1}, [%2];" : "=r"(v.x), "=r"(v.y) : "l"(p) : "memory"); return v;
}
__device__ __forceinline__ uint32_t ld_relaxed1(const void* p) {
    uint32_t v; asm volatile("ld.relaxed.gpu.global.u32 %0, [%1];" : "=r"(v) : "l"(p) : "memory"); return v;
}
__device__ __forceinline__ uint2 ldg_v2(const void* p) {
    uint2 v; asm volatile("ld.global.nc.v2.u32 {%0,%1}, [%2];" : "=r"(v.x), "=r"(v.y) : "l"(p)); return v;
}
__device__ __forceinline__ float bflo(uint32_t v) { return __uint_as_float(v << 16); }
__device__ __forceinline__ float bfhi(uint32_t v) { return __uint_as_float(v & 0xffff0000u); }
__device__ __forceinline__ uint32_t packbf(float lo, float hi) {
    uint32_t r; asm("cvt.rn.bf16x2.f32 %0, %1, %2;" : "=r"(r) : "f"(hi), "f"(lo)); return r;
}
__device__ __forceinline__ uint32_t packh(float lo, float hi) {
    uint32_t r; asm("cvt.rn.f16x2.f32 %0, %1, %2;" : "=r"(r) : "f"(hi), "f"(lo)); return r;
}
__device__ __forceinline__ float rbf(float x) { return __uint_as_float(packbf(0.f, x)); }
__device__ __forceinline__ uint32_t opaque(uint32_t v) { asm volatile("" : "+r"(v)); return v; }
__device__ __forceinline__ uint32_t bsub2(uint32_t a, uint32_t b) { uint32_t r; asm("sub.rn.bf16x2 %0, %1, %2;" : "=r"(r) : "r"(a), "r"(b)); return r; }
__device__ __forceinline__ uint32_t badd2(uint32_t a, uint32_t b) { uint32_t r; asm("add.rn.bf16x2 %0, %1, %2;" : "=r"(r) : "r"(a), "r"(b)); return r; }
__device__ __forceinline__ uint32_t bmul2(uint32_t a, uint32_t b) { uint32_t r; asm("mul.rn.bf16x2 %0, %1, %2;" : "=r"(r) : "r"(a), "r"(b)); return r; }
__device__ __forceinline__ uint32_t bfma2(uint32_t a, uint32_t b, uint32_t c) { uint32_t r; asm("fma.rn.bf16x2 %0, %1, %2, %3;" : "=r"(r) : "r"(a), "r"(b), "r"(c)); return r; }
__device__ __forceinline__ uint32_t bamax2(uint32_t a, uint32_t b) { uint32_t r; asm("max.xorsign.abs.bf16x2 %0, %1, %2;" : "=r"(r) : "r"(a), "r"(b)); return r; }
__device__ __forceinline__ uint32_t norm2(uint32_t x, uint32_t m, uint32_t hi, uint32_t lo) {
    uint32_t d = bsub2(x, m);
    return bfma2(d, hi, bmul2(d, lo));
}
__device__ __forceinline__ float ex2f(float x) { float r; asm("ex2.approx.ftz.f32 %0, %1;" : "=f"(r) : "f"(x)); return r; }
__device__ __forceinline__ float rcpf(float x) { float r; asm("rcp.approx.ftz.f32 %0, %1;" : "=f"(r) : "f"(x)); return r; }
__device__ __forceinline__ float siluf_(float x) {
    const float h = 0.5f * x;
    float th; asm("tanh.approx.f32 %0, %1;" : "=f"(th) : "f"(h));
    return fmaf(h, th, h);
}
__device__ __forceinline__ float sigmoidf_(float x) { return rcpf(1.f + ex2f(-1.4426950408889634f * x)); }
__device__ __forceinline__ uint32_t lds32(uint32_t a) { uint32_t v; asm volatile("ld.shared.u32 %0, [%1];" : "=r"(v) : "r"(a)); return v; }
__device__ __forceinline__ float lds32f(uint32_t a) { float v; asm volatile("ld.shared.f32 %0, [%1];" : "=f"(v) : "r"(a)); return v; }
__device__ __forceinline__ uint2 lds64(uint32_t a) { uint2 v; asm volatile("ld.shared.v2.u32 {%0,%1}, [%2];" : "=r"(v.x), "=r"(v.y) : "r"(a)); return v; }
__device__ __forceinline__ float2 lds64f(uint32_t a) { float2 v; asm volatile("ld.shared.v2.f32 {%0,%1}, [%2];" : "=f"(v.x), "=f"(v.y) : "r"(a)); return v; }
__device__ __forceinline__ uint4 lds128(uint32_t a) {
    uint4 v; asm volatile("ld.shared.v4.u32 {%0,%1,%2,%3}, [%4];" : "=r"(v.x), "=r"(v.y), "=r"(v.z), "=r"(v.w) : "r"(a)); return v;
}
__device__ __forceinline__ float4 lds128f(uint32_t a) {
    float4 v; asm volatile("ld.shared.v4.f32 {%0,%1,%2,%3}, [%4];" : "=f"(v.x), "=f"(v.y), "=f"(v.z), "=f"(v.w) : "r"(a)); return v;
}
__device__ __forceinline__ void sts32(uint32_t a, uint32_t v) { asm volatile("st.shared.u32 [%0], %1;" :: "r"(a), "r"(v)); }
__device__ __forceinline__ void sts32f(uint32_t a, float v) { asm volatile("st.shared.f32 [%0], %1;" :: "r"(a), "f"(v)); }
__device__ __forceinline__ void sts64(uint32_t a, uint32_t x, uint32_t y) { asm volatile("st.shared.v2.u32 [%0], {%1,%2};" :: "r"(a), "r"(x), "r"(y)); }
__device__ __forceinline__ void sts64f(uint32_t a, float x, float y) { asm volatile("st.shared.v2.f32 [%0], {%1,%2};" :: "r"(a), "f"(x), "f"(y)); }
__device__ __forceinline__ void sts128(uint32_t a, uint32_t x, uint32_t y, uint32_t z, uint32_t w) {
    asm volatile("st.shared.v4.u32 [%0], {%1,%2,%3,%4};" :: "r"(a), "r"(x), "r"(y), "r"(z), "r"(w));
}
__device__ __forceinline__ void ldsm4(uint32_t* r, uint32_t a) {
    asm volatile("ldmatrix.sync.aligned.m8n8.x4.shared.b16 {%0,%1,%2,%3}, [%4];" : "=r"(r[0]), "=r"(r[1]), "=r"(r[2]), "=r"(r[3]) : "r"(a));
}
__device__ __forceinline__ void ldsm2(uint32_t* r, uint32_t a) {
    asm volatile("ldmatrix.sync.aligned.m8n8.x2.shared.b16 {%0,%1}, [%2];" : "=r"(r[0]), "=r"(r[1]) : "r"(a));
}
__device__ __forceinline__ void ldsm4t(uint32_t* r, uint32_t a) {
    asm volatile("ldmatrix.sync.aligned.m8n8.x4.trans.shared.b16 {%0,%1,%2,%3}, [%4];" : "=r"(r[0]), "=r"(r[1]), "=r"(r[2]), "=r"(r[3]) : "r"(a));
}
__device__ __forceinline__ void ldsm2t(uint32_t* r, uint32_t a) {
    asm volatile("ldmatrix.sync.aligned.m8n8.x2.trans.shared.b16 {%0,%1}, [%2];" : "=r"(r[0]), "=r"(r[1]) : "r"(a));
}
__device__ __forceinline__ void stsm4t(uint32_t a, uint32_t x, uint32_t y, uint32_t z, uint32_t w) {
    asm volatile("stmatrix.sync.aligned.m8n8.x4.trans.shared.b16 [%0], {%1,%2,%3,%4};" :: "r"(a), "r"(x), "r"(y), "r"(z), "r"(w));
}
__device__ __forceinline__ void stsm4(uint32_t a, uint32_t x, uint32_t y, uint32_t z, uint32_t w) {
    asm volatile("stmatrix.sync.aligned.m8n8.x4.shared.b16 [%0], {%1,%2,%3,%4};" :: "r"(a), "r"(x), "r"(y), "r"(z), "r"(w));
}
__device__ __forceinline__ void mma_bf(float* d, uint32_t a0, uint32_t a1, uint32_t a2, uint32_t a3,
                                       uint32_t b0, uint32_t b1, const float* c) {
    asm("mma.sync.aligned.m16n8k16.row.col.f32.bf16.bf16.f32 {%0,%1,%2,%3}, {%4,%5,%6,%7}, {%8,%9}, {%10,%11,%12,%13};"
        : "=f"(d[0]), "=f"(d[1]), "=f"(d[2]), "=f"(d[3])
        : "r"(a0), "r"(a1), "r"(a2), "r"(a3), "r"(b0), "r"(b1), "f"(c[0]), "f"(c[1]), "f"(c[2]), "f"(c[3]));
}
__device__ __forceinline__ void mma_hh(uint32_t* d, const uint32_t* a, uint32_t b0, uint32_t b1) {
    asm("mma.sync.aligned.m16n8k16.row.col.f16.f16.f16.f16 {%0,%1}, {%2,%3,%4,%5}, {%6,%7}, {%0,%1};"
        : "+r"(d[0]), "+r"(d[1]) : "r"(a[0]), "r"(a[1]), "r"(a[2]), "r"(a[3]), "r"(b0), "r"(b1));
}
__device__ __forceinline__ uint32_t hadd2(uint32_t a, uint32_t b) { uint32_t r; asm("add.rn.f16x2 %0, %1, %2;" : "=r"(r) : "r"(a), "r"(b)); return r; }
__device__ __forceinline__ void mma_h8(uint32_t* d, uint32_t a0, uint32_t a1, uint32_t b0) {
    asm("mma.sync.aligned.m16n8k8.row.col.f16.f16.f16.f16 {%0,%1}, {%2,%3}, {%4}, {%0,%1};"
        : "+r"(d[0]), "+r"(d[1]) : "r"(a0), "r"(a1), "r"(b0));
}
__device__ __forceinline__ void mma_h(float* d, uint32_t a0, uint32_t a1, uint32_t a2, uint32_t a3, uint32_t b0, uint32_t b1) {
    asm("mma.sync.aligned.m16n8k16.row.col.f32.f16.f16.f32 {%0,%1,%2,%3}, {%4,%5,%6,%7}, {%8,%9}, {%0,%1,%2,%3};"
        : "+f"(d[0]), "+f"(d[1]), "+f"(d[2]), "+f"(d[3])
        : "r"(a0), "r"(a1), "r"(a2), "r"(a3), "r"(b0), "r"(b1));
}
__device__ __forceinline__ void st_async64(uint32_t a, uint32_t x, uint32_t y, uint32_t mb) {
    asm volatile("st.async.weak.shared::cluster.mbarrier::complete_tx::bytes.v2.b32 [%0], {%1,%2}, [%3];" :: "r"(a), "r"(x), "r"(y), "r"(mb) : "memory");
}
__device__ __forceinline__ void wgmma32z(uint32_t* d, const uint32_t* a, uint64_t desc) {
    asm volatile("wgmma.mma_async.sync.aligned.m64n32k16.f16.f16.f16 {%0,%1,%2,%3,%4,%5,%6,%7}, {%8,%9,%10,%11}, %12, 0, 1, 1, 0;"
                 : "=r"(d[0]), "=r"(d[1]), "=r"(d[2]), "=r"(d[3]), "=r"(d[4]), "=r"(d[5]), "=r"(d[6]), "=r"(d[7])
                 : "r"(a[0]), "r"(a[1]), "r"(a[2]), "r"(a[3]), "l"(desc));
}
template <int ACC>
__device__ __forceinline__ void wgmma32(uint32_t* d, const uint32_t* a, uint64_t desc) {
    asm volatile("wgmma.mma_async.sync.aligned.m64n32k16.f16.f16.f16 {%0,%1,%2,%3,%4,%5,%6,%7}, {%8,%9,%10,%11}, %12, %13, 1, 1, 0;"
                 : "+r"(d[0]), "+r"(d[1]), "+r"(d[2]), "+r"(d[3]), "+r"(d[4]), "+r"(d[5]), "+r"(d[6]), "+r"(d[7])
                 : "r"(a[0]), "r"(a[1]), "r"(a[2]), "r"(a[3]), "l"(desc), "n"(ACC));
}
template <int ACC>
__device__ __forceinline__ void wgmma8(float* d, uint64_t da, uint64_t db) {
    asm volatile("wgmma.mma_async.sync.aligned.m64n8k16.f32.bf16.bf16 {%0,%1,%2,%3}, %4, %5, %6, 1, 1, 1, 0;"
                 : "+f"(d[0]), "+f"(d[1]), "+f"(d[2]), "+f"(d[3]) : "l"(da), "l"(db), "n"(ACC));
}
__device__ __forceinline__ uint64_t mkdesc(uint32_t a, uint32_t lbo, uint32_t sbo, uint32_t swz) {
    return (uint64_t)(((a & 0x3ffff) >> 4) | ((lbo >> 4) << 16)) | ((uint64_t)((sbo >> 4) | (swz << 30)) << 32);
}
__device__ __forceinline__ uint32_t hmul2_(uint32_t a, uint32_t b) { uint32_t r; asm("mul.rn.f16x2 %0, %1, %2;" : "=r"(r) : "r"(a), "r"(b)); return r; }
__device__ __forceinline__ void st_async128(uint32_t a, uint32_t x, uint32_t y, uint32_t z, uint32_t w, uint32_t mb) {
    asm volatile("st.async.weak.shared::cluster.mbarrier::complete_tx::bytes.v4.b32 [%0], {%1,%2,%3,%4}, [%5];"
                 :: "r"(a), "r"(x), "r"(y), "r"(z), "r"(w), "r"(mb) : "memory");
}

__device__ __forceinline__ uint32_t stat_slot(uint32_t row) { return ((row >> 1) & ~7u) | ((row & 2) << 1) | ((row >> 2) & 3); }

struct cf { float r, i; };
__device__ __forceinline__ cf cmul(cf a, cf b) { return {fmaf(a.r, b.r, -a.i * b.i), fmaf(a.r, b.i, a.i * b.r)}; }
__device__ __forceinline__ cf cmulc(cf a, cf b) { return {fmaf(a.r, b.r, a.i * b.i), fmaf(a.i, b.r, -a.r * b.i)}; }
__device__ __forceinline__ cf csq(cf a) { return {fmaf(a.r, a.r, -a.i * a.i), (a.r + a.r) * a.i}; }
__device__ __forceinline__ cf cexp_(float a2, float th) {
    const float mag = ex2f(a2);
    float sn, cs;
    asm("sin.approx.ftz.f32 %0, %1;" : "=f"(sn) : "f"(th));
    asm("cos.approx.ftz.f32 %0, %1;" : "=f"(cs) : "f"(th));
    return {mag * cs, mag * sn};
}
__device__ __forceinline__ uint32_t hcmul(uint32_t z, uint32_t w, uint32_t wr) {
    __half2 zz = *reinterpret_cast<__half2*>(&z);
    __half2 r = __hfma2(__high2half2(zz), *reinterpret_cast<__half2*>(&wr),
                        __hmul2(__low2half2(zz), *reinterpret_cast<__half2*>(&w)));
    return *reinterpret_cast<uint32_t*>(&r);
}

#define LANEVARS int lane; asm volatile("mov.u32 %0, %%laneid;" : "=r"(lane));                     \
    const int g = lane >> 2, t = lane & 3, mi = lane >> 3, rr = lane & 7;                           \
    const uint32_t cl16 = cb + lane * 16; (void)g; (void)t; (void)mi; (void)rr; (void)cl16;

__device__ __forceinline__ void sum4(uint32_t* w, uint32_t ra) {
    const uint4 p0 = lds128(ra), p1 = lds128(ra + 1536), p2 = lds128(ra + 3072), p3 = lds128(ra + 4608);
    w[0] = hadd2(hadd2(p0.x, p1.x), hadd2(p2.x, p3.x)); w[1] = hadd2(hadd2(p0.y, p1.y), hadd2(p2.y, p3.y));
    w[2] = hadd2(hadd2(p0.z, p1.z), hadd2(p2.z, p3.z)); w[3] = hadd2(hadd2(p0.w, p1.w), hadd2(p2.w, p3.w));
#pragma unroll
    for (int i = 0; i < 4; i++) w[i] = hmul2_(w[i], 0x10001000u);
}

__device__ __forceinline__ void windows(const uint32_t sb, const int ch, const int po) {
    const uint32_t cb = sb + OFF_CH + ch * CHS, bars = sb + OFF_BAR;
    LANEVARS
    const uint32_t ub = bars + BAR_U * 8 + (po >> 4);
    if (!(mbar_try(ub) & mbar_try(ub + 8) & mbar_try(ub + 16) & mbar_try(ub + 24))) {
#pragma unroll 1
        for (int i = 0; i < 32; i += 8) mbar_wait(ub + i);
    }
    const uint32_t wa = cl16 + po;
    const uint32_t wu = sb + OFF_U + ch * UCH + 128 + lane * 16 + po;
    const uint4 ra = lds128(wu - 16), rb = lds128(wu + UPL - 16), rc = lds128(wu), rd = lds128(wu + UPL);
    const uint32_t e[13] = {ra.z, ra.w, rb.x, rb.y, rb.z, rb.w, rc.x, rc.y, rc.z, rc.w, rd.x, rd.y, rd.z};
    uint32_t w2[12], w3[12], p4[11], w5[11];
#pragma unroll
    for (int i = 0; i < 12; i++) {
        const uint32_t o = __byte_perm(e[i], e[i + 1], 0x5432);
        w2[i] = hadd2(e[i], o);
        if (i < 11) w3[i + 1] = o;
        if (i > 0) w3[i] = hadd2(w3[i], w2[i]);
        if (i > 0 && i < 11) p4[i] = hadd2(w2[i - 1], w2[i]);
        if (i > 1 && i < 11) w5[i] = hadd2(p4[i], e[i + 1]);
    }
#pragma unroll
    for (int k = 0; k < 8; k += 4) {
        sts128(wa + k * (PL / 4) + C_A3, w3[4 + k], w3[5 + k], w3[6 + k], w3[7 + k]);
        sts128(wa + k * (PL / 4) + C_W5, w5[2 + k], w5[3 + k], w5[4 + k], w5[5 + k]);
    }
    if (po < 1024) {
#pragma unroll
        for (int k = 0; k < 8; k += 4) {
            sts128(wa + k * (PL / 4) + C_Z5, w2[4 + k], w2[5 + k], w2[6 + k], w2[7 + k]);
            sts128(wa + k * (PL / 4) + C_W7, hadd2(w3[1 + k], p4[3 + k]), hadd2(w3[2 + k], p4[4 + k]),
                   hadd2(w3[3 + k], p4[5 + k]), hadd2(w3[4 + k], p4[6 + k]));
            sts128(wa + k * (PL / 4) + C_W9, hadd2(p4[1 + k], w5[3 + k]), hadd2(p4[2 + k], w5[4 + k]),
                   hadd2(p4[3 + k], w5[5 + k]), hadd2(p4[4 + k], w5[6 + k]));
        }
    }
}

struct Maps { CUtensorMap x, o, w[3]; const char* wp[3]; };

__global__ void __cluster_dims__(2, 1, 1) __launch_bounds__(640, 1)
fused_kernel(const uint2* __restrict__ p_lar, const uint2* __restrict__ p_aim, const uint2* __restrict__ p_cr,
             const uint2* __restrict__ p_ci, const uint16_t* __restrict__ p_ldt, const uint16_t* __restrict__ p_dsk,
             const uint4* __restrict__ x, Scratch* sc, const uint4* __restrict__ p_wr, uint16_t* __restrict__ out, const __grid_constant__ Maps tm) {
    extern __shared__ __align__(1024) uint8_t smem_raw[];
    const uint32_t sb = (uint32_t)__cvta_generic_to_shared(smem_raw);
    const int pwarp = __shfl_sync(~0u, threadIdx.x >> 5, 0), lane = threadIdx.x & 31;
    const int warp = pwarp;
    const int b = blockIdx.x, cl = b >> 1, rk = b & 1;
    const int g = lane >> 2, t = lane & 3, mi = lane >> 3, rr = lane & 7;
    const uint32_t t0 = clock();
    const uint32_t bars = sb + OFF_BAR;
    TS_INIT

    const int ch = warp & 3, kw = warp >> 2;
    const uint32_t cb = sb + OFF_CH + ch * CHS;
    const uint32_t cl16 = cb + lane * 16;
    const uint32_t flg = sb + OFF_FLG + ch * 16;
    const int j = (warp - 12) ^ JSWAP, s = 2 * j + rk;
    auto load_cols = [&](int jj) {
        asm volatile("cp.async.bulk.tensor.3d.shared::cluster.global.mbarrier::complete_tx::bytes [%0], [%1, {%3, %4, %5}], [%2];"
                     :: "r"(sb + OFF_XS + jj * 2048), "l"(&tm.x), "r"(bars + (BAR_X + jj) * 8), "r"(cl * 8), "r"((2 * jj + rk) * 32), "r"(0) : "memory");
    };

    auto load_w = [&]() {
        if (b < NFFN) {
#pragma unroll
            for (int i = 0; i < 3; i++)
                asm volatile("cp.async.bulk.tensor.3d.shared::cluster.global.mbarrier::complete_tx::bytes [%0], [%1, {%3, %4, %5}], [%2];"
                             :: "r"(sb + OFF_WG + i * 16384), "l"(&tm.w[i]), "r"(bars + BAR_W * 8),
                                "r"(i < 2 ? b * 16 : 0), "r"(i < 2 ? 0 : b * 16), "r"(0) : "memory");
        }
    };
    auto prefetch_w = [&](int m) {
        if (elect_one())
            asm volatile("cp.async.bulk.prefetch.L2.global [%0], 2752;" :: "l"(tm.wp[m] + (4 * b + ch) * 2752) : "memory");
        __syncwarp();
    };

    if (warp < 16) {
        if (kw == 3) {
            if (elect_one()) {
                const uint32_t bi = bars + ch * 8;
#pragma unroll
                for (int i = 0; i < 10; i++)
                    asm volatile("mbarrier.init.shared::cta.b64 [%0], %1;" :: "r"(bi + i * 32), "r"((i & 6) == 6 ? 3 : 1) : "memory");
#pragma unroll
                for (int i = 0; i < 10; i++)
                    if (i >= 4 || (ch & 1) != rk)
                        asm volatile("mbarrier.arrive.expect_tx.shared::cta.b64 _, [%0], %1;"
                                     :: "r"(bi + i * 32), "r"(i == 9 ? 4096 : i == 8 && ch == 0 ? 49152 : (i & 6) == 4 ? 2048 : 1024) : "memory");
                if (ch == 1)
                    asm volatile("cp.async.bulk.shared::cluster.global.mbarrier::complete_tx::bytes [%0], [%1], 1024, [%2];"
                                 :: "r"(sb + OFF_WR), "l"(p_wr), "r"(bars + (BAR_W + 1) * 8) : "memory");
                asm volatile("prefetch.tensormap [%0];" :: "l"(&tm.x + (ch ? ch + 1 : 0)) : "memory");
                asm volatile("fence.mbarrier_init.release.cluster;" ::: "memory");
            }
            __syncwarp();
            if (lane < 16) sts128(sb + OFF_U + ch * UCH + mi * UPL + rr * 16, 0, 0, 0, 0);
            sts32(sb + OFF_FLG + 64 + rr * 4, 0);
            sts128(sb + OFF_RK + 32, 0, 0, 0, 0);
        }
        asm volatile("barrier.cluster.arrive.relaxed.aligned;" ::: "memory");
        const int d = 8 * cl + 2 * ch + rk;
        uint2 lar4, aim4, cr4, ci4;
        uint32_t ldt, dsk;
        {
            const uint64_t off = opaque(d * 256 + lane * 8), off2 = opaque(d * 2);
            asm volatile("ld.global.nc.v2.u32 {%0,%1}, [%10]; ld.global.nc.v2.u32 {%2,%3}, [%11];\n"
                         "ld.global.nc.u16 %8, [%14];\n"
                         "ld.global.nc.v2.u32 {%4,%5}, [%12]; ld.global.nc.v2.u32 {%6,%7}, [%13];\n"
                         "ld.global.nc.u16 %9, [%15];"
                         : "=r"(lar4.x), "=r"(lar4.y), "=r"(aim4.x), "=r"(aim4.y), "=r"(cr4.x), "=r"(cr4.y), "=r"(ci4.x), "=r"(ci4.y),
                           "=r"(ldt), "=r"(dsk)
                         : "l"((const char*)p_lar + off), "l"((const char*)p_aim + off), "l"((const char*)p_cr + off),
                           "l"((const char*)p_ci + off), "l"((const char*)p_ldt + off2), "l"((const char*)p_dsk + off2));
        }
        const uint32_t tw = cb + kw * (8 * KG_STRIDE);
        const uint32_t ta = opaque(tw + rr * KG_STRIDE + mi * 16);
        const uint32_t tk_ = tw + (mi & 1) * KG_STRIDE;
        const uint32_t a1 = opaque(tw + (mi >> 1) * KG_STRIDE + ((mi & 1) ? 24 * 16 : rr * 16));
        const uint32_t a3 = opaque(tk_ + 128 + (mi & 2) * 64 + rr * 16);
        const uint32_t a4 = opaque(tk_ + (rr < 5 ? 25 + rr : rr == 5 ? 16 : 15) * 16);
        const uint32_t kp = opaque(cb + C_KP + kw * 1536 + lane * 16);
        const uint32_t kp2 = opaque(cb + C_KP + kw * 1536 + 1024 + rr * 64 + (mi ^ (rr >> 1)) * 16);
        const uint32_t cm = sb + OFF_CH + 2 * kw * CHS;
        const int cc = 2 * kw + (ch >> 1); (void)cc;
        const uint32_t wt = opaque(cm + (ch >> 1) * CHS + C_WT + lane * 32), wa = opaque(cm + C_WT + (144 * ch + g - 2 * t) * 4);
        const uint32_t rw = opaque(cm + C_RG + ch * 2 * RPL + (mi & 1) * RPL);
        uint32_t o0 = opaque((9 * ch + (mi >> 1) * 8 + rr) * 16), o1;
        const uint32_t rs = opaque(cm + (lane >> 4) * CHS + C_RG + (lane & 1) * RPL + (8 * ch + ((lane >> 1) & 7)) * 16);
        const uint32_t ya = opaque(mapa(sb + OFF_Y + (ch >> 1) * 2048 + (4 * rk + 2 * kw) * 256 + lane * 16, ch & 1));
        const uint32_t ra4 = opaque(kw < 2 ? cm + (ch >> 1) * CHS + C_KP + (ch & 1) * 512 + lane * 16 : cb + C_KP + 1024 + (lane ^ mi) * 16);
        if (kw == 3) {
            if (elect_one()) {
#pragma unroll 1
                for (int jj = ch; jj < 8; jj += 4) {
                    while ((uint32_t)clock() - t0 < (uint32_t)(CSTART + CSTEP * jj)) {}
                    load_cols(jj);
                }
            }
            __syncwarp();
            TS(21);
        }
        const uint32_t dtb = packbf(0.f, ex2f(bflo(ldt) * 1.4426950408889634f));
        const float dt = __uint_as_float(dtb);
        uint32_t mx = bamax2(bamax2(cr4.x, ci4.x), bamax2(cr4.y, ci4.y));
        mx = __reduce_max_sync(~0u, bamax2(mx, mx << 16) & 0x7f800000u);
        const int ed = (int)((dsk << 16) & 0x7f800000u) - (int)(dtb & 0x7f800000u) + (113 << 23);
        const uint32_t e = min(max(max((int)mx, ed), 0x00800000), 0x7e800000);
        const float cinv = __uint_as_float(0x7f000000u - e + (dtb & 0x007fffffu));
        const float fs = 2.f * __uint_as_float(dtb & 0x7f800000u) * __uint_as_float(e);
        sts32(sb + OFF_RK + ch * 4, packbf(fs * 2048.f, fs * 2048.f));
        TS(0);
        {
            const uint32_t sel = 0x1044 + kw * 0x2200;
            const float a2 = rbf(ex2f(bfhi(__byte_perm(lar4.x, lar4.y, sel)) * 1.4426950408889634f)) * dt * -1.4426950408889634f;
            const float th = bfhi(__byte_perm(aim4.x, aim4.y, sel)) * dt;
            const cf c0 = {bfhi(__byte_perm(cr4.x, cr4.y, sel)) * cinv, bfhi(__byte_perm(ci4.x, ci4.y, sel)) * -cinv};
            const cf w1 = cexp_(a2, th), w64 = cexp_(a2 * 64.f, th * 64.f);
            const cf w2 = csq(w1), w3 = cmul(w2, w1), w4 = csq(w2), w8 = csq(w4), w16 = csq(w8), w32 = csq(w16);
            const cf w128 = csq(w64), w256 = csq(w128), w512 = csq(w256);
            const cf w1k = csq(w512);
            const cf c1 = cmulc(c0, w8), c2 = cmulc(c0, w16), c3 = cmulc(c1, w16);
            const uint32_t s1 = packh(w1.r, w1.i), s2 = packh(w2.r, w2.i), s3 = packh(w3.r, w3.i);
            const uint32_t s4 = packh(w4.r, w4.i), s4r = packh(-w4.i, w4.r);
            const uint32_t s6 = hcmul(s2, s4, s4r);
            stsm4(ta + 128, 0x00003c00u, s1, s2, s3);
            stsm4(ta + 192, s4, hcmul(s1, s4, s4r), s6, hcmul(s3, s4, s4r));
            const uint32_t v0 = packh(w256.r, w256.i), v1 = packh(w512.r, w512.i), v0r = packh(-w256.i, w256.r);
            const uint32_t v3 = packh(w1k.r, w1k.i), v3r = packh(-w1k.i, w1k.r), v2 = hcmul(v1, v0, v0r);
            stsm4(ta + 384, packh(w64.r, -w64.i), v0, hcmul(s2, v0, v0r), hcmul(v0, s4, s4r));
            stsm4(ta + 256, v1, v2, v3, hcmul(v0, v3, v3r));
            stsm4(ta + 320, hcmul(v1, v3, v3r), hcmul(v2, v3, v3r), hcmul(v1, s4, s4r), hcmul(v2, s4, s4r));
            asm volatile("stmatrix.sync.aligned.m8n8.x2.shared.b16 [%0], {%1,%2};" :: "r"(ta + 448), "r"(hcmul(s6, v0, v0r)), "r"(hcmul(v3, v3, v3r)));
            const uint32_t e0 = packh(c0.r, c0.i), e1 = packh(c1.r, c1.i), e2 = packh(c2.r, c2.i), e3 = packh(c3.r, c3.i);
            const uint32_t h32 = packh(w32.r, -w32.i), h32r = packh(w32.i, w32.r);
            stsm4(ta, e0, e1, e2, e3);
            stsm4(ta + 64, hcmul(e0, h32, h32r), hcmul(e1, h32, h32r), hcmul(e2, h32, h32r), hcmul(e3, h32, h32r));
        }
        __syncwarp();
        TS(1);
        bar_sync(12, 640);
        if (kw == 2) prefetch_w(0);
        float KD[2][3][4];
#pragma unroll
        for (int m = 0; m < 2; m++)
#pragma unroll
            for (int n = 0; n < 3; n++)
#pragma unroll
                for (int i = 0; i < 4; i++) KD[m][n][i] = 0.f;
        if (threadIdx.x < 128 && lane == 0) KD[0][0][0] = bflo(dsk) * rcpf(fs);
#pragma unroll 1
        for (int ko = 0; ko < 8 * KG_STRIDE; ko += 2 * KG_STRIDE) {
            uint32_t eu[4], sv[4], qq[2];
            ldsm4(eu, a1 + ko); ldsm4(sv, a3 + ko); ldsm2(qq, a4 + ko);
            const uint32_t uar = __byte_perm(eu[1], 0, 0x1032) ^ 0x00008000u, ubr = __byte_perm(eu[3], 0, 0x1032) ^ 0x00008000u;
            uint32_t x2[4];
            asm("{.reg .b16 l, h; .reg .b32 ll, hh, t, u;\n"
                "mov.b32 u, %0; mov.b32 {l, h}, %3; mov.b32 ll, {l, l}; mov.b32 hh, {h, h}; mul.rn.f16x2 t, ll, u; fma.rn.f16x2 %0, hh, %4, t;\n"
                "mov.b32 {l, h}, %0; mov.b32 ll, {l, l}; mov.b32 hh, {h, h}; mul.rn.f16x2 t, ll, u; fma.rn.f16x2 %1, hh, %4, t;\n"
                "mov.b32 {l, h}, %1; mov.b32 ll, {l, l}; mov.b32 hh, {h, h}; mul.rn.f16x2 t, ll, u; fma.rn.f16x2 %2, hh, %4, t;}"
                : "+r"(eu[1]), "=r"(x2[0]), "=r"(x2[1]) : "r"(eu[0]), "r"(uar));
            asm("{.reg .b16 l, h; .reg .b32 ll, hh, t, u;\n"
                "mov.b32 u, %0; mov.b32 {l, h}, %3; mov.b32 ll, {l, l}; mov.b32 hh, {h, h}; mul.rn.f16x2 t, ll, u; fma.rn.f16x2 %0, hh, %4, t;\n"
                "mov.b32 {l, h}, %0; mov.b32 ll, {l, l}; mov.b32 hh, {h, h}; mul.rn.f16x2 t, ll, u; fma.rn.f16x2 %1, hh, %4, t;\n"
                "mov.b32 {l, h}, %1; mov.b32 ll, {l, l}; mov.b32 hh, {h, h}; mul.rn.f16x2 t, ll, u; fma.rn.f16x2 %2, hh, %4, t;}"
                : "+r"(eu[3]), "=r"(x2[2]), "=r"(x2[3]) : "r"(eu[2]), "r"(ubr));
            mma_h(KD[0][0], eu[0], eu[1], eu[2], eu[3], sv[0], sv[1]);
            mma_h(KD[0][2], eu[0], eu[1], eu[2], eu[3], sv[2], sv[3]);
            mma_h(KD[0][1], eu[0], eu[1], eu[2], eu[3], qq[0], qq[1]);
            mma_h(KD[1][0], x2[0], x2[1], x2[2], x2[3], sv[0], sv[1]);
            mma_h(KD[1][2], x2[0], x2[1], x2[2], x2[3], sv[2], sv[3]);
            mma_h(KD[1][1], x2[0], x2[1], x2[2], x2[3], qq[0], qq[1]);
        }
#define PK(n) packh(KD[0][n][0], KD[0][n][1]), packh(KD[0][n][2], KD[0][n][3]), packh(KD[1][n][0], KD[1][n][1]), packh(KD[1][n][2], KD[1][n][3])
        stsm4(kp, PK(0));
        stsm4(kp + 512, PK(1));
        stsm4t(kp2, PK(2));
        TS(2);
        if (kw < 2) {
            asm volatile("barrier.cluster.wait.acquire.aligned;" ::: "memory");
            const uint32_t yb = mapa(bars + (BAR_Y + (ch >> 1)) * 8, ch & 1);
            const uint64_t desc = mkdesc(sb + OFF_U + 2 * kw * UCH + 128, UPL, 128, 0);
            bar_sync(13, 512);
            const uint32_t zero = lds32(sb + OFF_U), fs2 = lds32(sb + OFF_RK + kw * 8 + (lane >> 4) * 4);
            TS(6);
            {
                uint32_t w[4];
                sum4(w, ra4);
                const uint32_t wp = __shfl_sync(~0u, w[3], lane - 1);
                if (!(ch & 1)) {
                    sts128(wt, __byte_perm(w[0], lane ? wp : 0u, 0x7610), __byte_perm(w[0], 0, 0x1032),
                           __byte_perm(w[1], w[0], 0x7610), __byte_perm(w[1], 0, 0x1032));
                    sts128(wt + 16, __byte_perm(w[2], w[1], 0x7610), __byte_perm(w[2], 0, 0x1032),
                           __byte_perm(w[3], w[2], 0x7610), __byte_perm(w[3], 0, 0x1032));
                } else {
                    const uint32_t wn = __shfl_sync(~0u, w[0], lane + 1), s0 = __shfl_sync(~0u, w[2], 0);
                    const uint32_t k44 = __byte_perm(w[1], 0, 0x1010), kk = __byte_perm(s0, 0, 0x3232);
                    sts128(wt + 1024, __byte_perm(w[0], lane ? w[0] : wp, 0x5410), __byte_perm(w[0], 0, 0x1010),
                           __byte_perm(w[0], 0, 0x1032), __byte_perm(w[1], w[0], 0x7610));
                    sts128(wt + 1040, k44, k44, __byte_perm(w[1], 0, 0x1032), __byte_perm(lane == 31 ? kk : wn, w[1], 0x7610));
                    const uint32_t ke = lane == 4 ? kk : 0u;
                    if (lane < 22) sts128(wt - lane * 16 - 64 + (lane < 4 ? 0 : 2048), ke, ke, ke, ke & 0xffff0000u);
                    sts32(sb + OFF_FLG + cc * 16 + 12, s0);
                }
            }
            asm volatile("setmaxnreg.inc.sync.aligned.u32 120;");
            bar_sync(14, 384);
            TS(8);
            uint32_t T[2][9][4], D[2][8];
            o1 = o0 + 256;
#pragma unroll
            for (int c = 0; c < 2; c++) {
                T[c][0][2] = lds32(wa + c * CHS - 32);
#pragma unroll
                for (int q = 0; q < 9; q++) { T[c][q][0] = lds32(wa + c * CHS + 64 * q); T[c][q][1] = lds32(wa + c * CHS + 64 * q + 32); }
            }
            const bool ok = mbar_try(bars) & mbar_try(bars + 8) & mbar_try(bars + 16) & mbar_try(bars + 24);
#pragma unroll
            for (int c = 0; c < 2; c++)
#pragma unroll
                for (int q = 0; q < 9; q++) {
                    asm volatile("add.u32 %0, %1, %2;" : "=r"(T[c][q][3]) : "r"(T[c][q][0]), "r"(zero));
                    if (q) asm volatile("xor.b32 %0, %1, %2;" : "=r"(T[c][q][2]) : "r"(T[c][q - 1][1]), "r"(zero));
                }
            TS(3);
            if (!ok) {
#pragma unroll 1
                for (int i = 0; i < 32; i += 8) mbar_wait(bars + i);
            }
            asm volatile("fence.proxy.async.shared::cta;" ::: "memory");
#pragma unroll 1
            for (int po = 0; po < 2048; po += 512) {
                if (kw) bar_sync(4 + ((po >> 9) & 1), 256);
                else if (po) bar_sync(po >> 9, 256);
                TS(9 + (po >> 9));
                asm volatile("wgmma.fence.sync.aligned;" ::: "memory");
                const uint64_t dc = desc + (po >> 4);
                wgmma32z(D[0], T[0][0], dc); wgmma32z(D[1], T[1][0], dc + (UCH >> 4));
#pragma unroll
                for (int q = 1; q < 9; q++) { wgmma32<1>(D[0], T[0][q], dc - q); wgmma32<1>(D[1], T[1][q], dc + (UCH >> 4) - q); }
                asm volatile("wgmma.commit_group.sync.aligned;" ::: "memory");
                if (kw == 0) bar_arrive(4 + ((po >> 9) & 1), 256);
                if (po == 0) {
                    if (lane < 9 * ch) {
                        const uint32_t za = cm + C_RG + ch * 2 * RPL + lane * 16;
                        sts128(za, 0, 0, 0, 0); sts128(za + RPL, 0, 0, 0, 0); sts128(za + CHS, 0, 0, 0, 0); sts128(za + CHS + RPL, 0, 0, 0, 0);
                    }
                    if (!(mbar_try(bars + 32 + 8 * ch) & mbar_try(bars + 64 + 8 * ch) & mbar_try(bars + 96 + 8 * ch))) {
#pragma unroll 1
                        for (int i = 32 + 8 * ch; i < 128; i += 32) mbar_wait(bars + i);
                    }
                }
                __syncwarp();
                asm volatile("wgmma.wait_group.sync.aligned 0;" ::: "memory");
                TS(14 + (po >> 9));
#pragma unroll
                for (int c = 0; c < 2; c++) {
                    asm volatile("" : "+r"(D[c][0]), "+r"(D[c][1]), "+r"(D[c][2]), "+r"(D[c][3]), "+r"(D[c][4]), "+r"(D[c][5]), "+r"(D[c][6]), "+r"(D[c][7]));
                    stsm4t(rw + c * CHS + o0, D[c][0], D[c][1], D[c][2], D[c][3]);
                    stsm4t(rw + c * CHS + o1, D[c][4], D[c][5], D[c][6], D[c][7]);
                }
                o0 += o0 < 1024 ? 512 : -1024; o1 += o1 < 1024 ? 512 : -1024;
                bar_sync(10 + kw, 128);
                const uint32_t ra = rs + (po < 1536 ? po : 0);
                const uint4 p1 = lds128(ra + 2 * RPL), p2 = lds128(ra + 4 * RPL), p3 = lds128(ra + 6 * RPL);
                const uint4 p4 = lds128(po ? rs + 8 * RPL - 512 + po : sb + OFF_U), p0 = lds128(ra);
                uint32_t yv[4] = {hadd2(p0.x, hadd2(hadd2(p1.x, p2.x), hadd2(p3.x, p4.x))), hadd2(p0.y, hadd2(hadd2(p1.y, p2.y), hadd2(p3.y, p4.y))),
                                  hadd2(p0.z, hadd2(hadd2(p1.z, p2.z), hadd2(p3.z, p4.z))), hadd2(p0.w, hadd2(hadd2(p1.w, p2.w), hadd2(p3.w, p4.w)))};
#pragma unroll
                for (int i = 0; i < 4; i++) {
                    const float2 f = __half22float2(*(const __half2*)&yv[i]);
                    yv[i] = bmul2(packbf(f.x, f.y), fs2);
                }
                if ((ch & 1) == rk) {
                    sts128(ya + po * 8, yv[0], yv[1], yv[2], yv[3]);
                    __syncwarp();
                    if (lane == 0) asm volatile("mbarrier.arrive.shared::cta.b64 _, [%0];" :: "r"(yb + (po >> 5)) : "memory");
                } else {
                    st_async128(ya + po * 8, yv[0], yv[1], yv[2], yv[3], yb + (po >> 5));
                }
                if (po == 0) asm volatile("fence.proxy.async.shared::cta;" ::: "memory");
                __syncwarp();
                TS(18 + (po >> 9));
            }
            TS(5);
            TS_DUMP
            return;
        }
        if (kw == 3) bar_arrive(13, 512);
        asm volatile("barrier.cluster.wait.acquire.aligned;" ::: "memory");
    } else {
        asm volatile("barrier.cluster.arrive.relaxed.aligned;" ::: "memory");
        const uint32_t tag = ld_relaxed1(sc->epoch + 8 * b + rr);
        const int row = 16 * b + 4 * ch + mi;
        uint4 xr[8];
        {
            const uint4* src = x + row * 64 + rr;
            while ((uint32_t)clock() - t0 < (uint32_t)(SBASE + STAGGER * (b >> 3))) {}
#pragma unroll
            for (int i = 0; i < 8; i++)
                asm volatile("ld.global.nc.v4.u32 {%0,%1,%2,%3}, [%4];" : "=r"(xr[i].x), "=r"(xr[i].y), "=r"(xr[i].z), "=r"(xr[i].w) : "l"(src + i * 8));
        }
        TS(17);
        asm volatile("barrier.cluster.wait.acquire.aligned;" ::: "memory");
        if (lane == 0)
            asm volatile("cp.async.bulk.shared::cluster.global.mbarrier::complete_tx::bytes [%0], [%1], 4096, [%2];"
                         :: "r"(sb + OFF_Y + ch * 4096), "l"(x + (16 * b + 4 * ch) * 64), "r"(bars + (BAR_R + ch) * 8) : "memory");
        __syncwarp();
        mbar_wait(bars + (BAR_W + 1) * 8);
        float a[4][4], rw[4], sw[4];
#pragma unroll
        for (int k = 0; k < 4; k++) a[0][k] = a[1][k] = a[2][k] = a[3][k] = rw[k] = sw[k] = 0.f;
        const uint32_t ONE = 0x3f803f80u;
        const uint32_t wa = sb + OFF_WR + (g & 2) * 32 + t * 16 + (g & 1) * 4;
#pragma unroll 1
        for (int i = 0; i < 1024; i += 256) {
            mma_bf(sw, ONE, ONE, ONE, ONE, lds32(wa + i), lds32(wa + i + 8), sw);
            mma_bf(rw, ONE, ONE, ONE, ONE, lds32(wa + i + 128), lds32(wa + i + 136), rw);
        }
        const float sumw = (sw[0] + sw[3]) + (rw[0] + rw[3]);
        TS(20);
#pragma unroll
        for (int i = 0; i < 8; i++) {
            mma_bf(a[(2 * i) & 3], xr[i].x, ONE, xr[i].y, ONE, xr[i].x, xr[i].y, a[(2 * i) & 3]);
            mma_bf(a[(2 * i + 1) & 3], xr[i].z, ONE, xr[i].w, ONE, xr[i].z, xr[i].w, a[(2 * i + 1) & 3]);
        }
        float sq = (g & 1) ? (a[0][1] + a[1][1]) + (a[2][1] + a[3][1]) : (a[0][0] + a[1][0]) + (a[2][0] + a[3][0]);
        TS(0);
        sq += __shfl_xor_sync(~0u, sq, 4);
        const float mean = (((a[0][2] + a[1][2]) + (a[2][2] + a[3][2])) + ((a[0][3] + a[1][3]) + (a[2][3] + a[3][3]))) * (1.f / 512.f);
        float var = fmaf(-mean, mean, sq * (1.f / 512.f));
        const int src = 9 * mi;
        if (lane == src && !(mean * mean <= 64.f * var)) {
            var = 0.f;
#pragma unroll 1
            for (int i = 0; i < 512; i++) {
                const float dv = bflo(__ldg((const uint16_t*)x + row * 512 + i)) - mean;
                var = fmaf(dv, dv, var);
            }
            var *= 1.f / 512.f;
        }
        __syncwarp();

        float sd;
        asm("sqrt.approx.ftz.f32 %0, %1;" : "=f"(sd) : "f"(rbf(rbf(var) + 1e-5f)));
        const float rs = rcpf(rbf(sd));
        const uint32_t w0 = packbf(mean, rs);
        if (lane == src) {
            const uint32_t sa = sb + OFF_ST + ch * 16 + (mi >> 1) * 64 + (mi & 1) * 2;
            asm volatile("st.shared.u16 [%0], %1; st.shared.u16 [%0+4], %2; st.shared.u16 [%0+8], %3; st.shared.u16 [%0+12], %4;"
                         :: "r"(sa), "h"((uint16_t)w0), "h"((uint16_t)(w0 >> 16)), "h"((uint16_t)packbf(rs - bfhi(w0), 0.f)), "h"((uint16_t)(tag + 1)) : "memory");
        }
        if (ch == 3) {
            bar_sync(8, 128);
            const uint4 v = lds128(sb + OFF_ST + rr * 16);
            asm volatile("st.relaxed.gpu.global.v4.u32 [%0], {%1,%2,%3,%4};" :: "l"(sc->stats + mi * (NCTA * 8) + 8 * b + rr),
                         "r"(v.x), "r"(v.y), "r"(v.z), "r"(v.w) : "memory");
        } else {
            bar_arrive(8, 128);
        }
        bar_arrive(12, 640);
        TS(1);
        if (lane == 0) {
            mbar_wait(bars + (BAR_R + ch) * 8);
            asm volatile("cp.async.bulk.global.shared::cta.bulk_group [%0], [%1], 4096;"
                         :: "l"(out + (16 * b + 4 * ch) * 512), "r"(sb + OFF_Y + ch * 4096) : "memory");
            asm volatile("cp.async.bulk.commit_group;" ::: "memory");
        }
        __syncwarp();
        const float z4[4] = {0.f, 0.f, 0.f, 0.f};
#pragma unroll
        for (int i = 0; i < 8; i++) {
            const uint32_t b0 = lds32(wa + i * 128), b1 = lds32(wa + i * 128 + 8);
            mma_bf(a[i & 1], xr[i].x, xr[i].y, xr[i].z, xr[i].w, b0, b1, i < 2 ? z4 : a[i & 1]);
        }
        float r = fmaf(-bflo(__shfl_sync(~0u, w0, src)), sumw, (a[0][0] + a[0][3]) + (a[1][0] + a[1][3]));
        r = (__shfl_sync(~0u, r, 8 * mi) + __shfl_sync(~0u, r, 8 * mi + 5)) * rs;
        {
            const uint32_t kb = packbf(0.f, r);
            uint32_t k = (kb ^ (uint32_t)((int32_t)kb >> 31 | 0x80000000)) & 0xffff0000u;
            if (r != r) k = 0;
            k |= (((tag + 1) & 31u) << 11) | (uint32_t)(2047 - row);
            k = __reduce_max_sync(~0u, lane == src ? k : 0u);
            sts32(sb + OFF_RK + 16 + ch * 4, k);
        }
        if (lane == 0) asm volatile("cp.async.bulk.wait_group 0;" ::: "memory");
        __syncwarp();
        if (ch == 3) {
            bar_sync(15, 128);
            const uint4 k = lds128(sb + OFF_RK + 16);
            if (lane < 8) asm volatile("st.relaxed.gpu.global.u32 [%0], %1;" :: "l"(sc->route + 8 * b + lane), "r"(max(max(k.x, k.y), max(k.z, k.w))) : "memory");
        } else {
            bar_arrive(15, 128);
        }
        TS(2);
    }

    if (warp < 12) {
        LANEVARS
        bar_sync(13, 512);
        if (warp == 8) st_flag(sb + OFF_RK + 44, 1);
        TS(6);
        uint32_t w[4];
        sum4(w, cb + C_KP + 1024 + (lane ^ mi) * 16);
        const uint32_t wp = __shfl_sync(~0u, w[3], lane - 1);
        uint32_t wn = __shfl_sync(~0u, w[0], lane + 1);
        const uint32_t cl32 = cl16 + lane * 16;
        {
            {
                const bool ez = lane >= 24;
                const uint32_t l0 = ez ? wp : w[0], l1 = ez ? w[0] : w[1], l2 = ez ? w[1] : w[2], l3 = ez ? w[2] : w[3], l4 = ez ? w[3] : wn;
                sts128(cl32 + C_PG, __byte_perm(w[0], wp, 0x7632), __byte_perm(l1, l0, 0x5410), __byte_perm(w[1], w[0], 0x7632), __byte_perm(l2, l1, 0x5410));
                sts128(cl32 + C_PG + 16, __byte_perm(w[2], w[1], 0x7632), __byte_perm(l3, l2, 0x5410), __byte_perm(w[3], w[2], 0x7632), __byte_perm(l4, l3, 0x5410));
                if (lane == 31) sts64(cb + C_PG + 1024, w[3], w[3] << 16);
                if (lane < 4) sts128(cb + PL + lane * 1040 + min(lane, 2) * 512, 0, 0, 0, 0);
            }
            prefetch_w(1); prefetch_w(2);
            TS(3);
            bar_sync(14, 384);
            {
            LANEVARS
            uint32_t B2[5][4], B3[8][2];
            const int dg = g - 2 * t;
            const uint32_t k1k = lds32(cb + C_PG + 31 * 8 + 4) & 0xffffu;
            const uint32_t bz = dg == 0 ? k1k : dg == 1 ? k1k << 16 : 0u;
            {
                const uint32_t pa = cb + C_PG + dg * 8;
                const uint32_t mu = dg < 0 ? 0u : dg == 0 ? 0xffffu : ~0u;
#pragma unroll
                for (int xx = 0; xx < 5; xx++) {
                    const uint2 v = lds64(pa + 64 * xx);
                    const uint2 ve = lds64(pa + 768 + 64 * xx);
                    B2[xx][0] = ve.x; B2[xx][1] = ve.y;
                    B2[xx][2] = v.x; B2[xx][3] = v.y;
                }
#pragma unroll
                for (int xx = 1; xx < 8; xx++) {
                    const uint2 v = lds64(pa + 256 + 64 * xx);
                    B3[xx][0] = v.x; B3[xx][1] = v.y;
                }

                const uint32_t k2k = lds32(flg + 12);
                if (lane == 28) B3[7][1] = __byte_perm(k2k, B3[7][1], 0x7610);
                B3[0][0] = B2[4][2] & mu; B3[0][1] = B2[4][3] & mu;
#pragma unroll
                for (int k = 0; k < 4; k++) { B2[0][k] &= mu; B2[4][k] &= ~mu; }
                asm volatile("" : "+r"(B3[0][0]), "+r"(B3[0][1]), "+r"(B2[4][2]), "+r"(B2[4][3]));
            }
            const int hx = (mi & 1) - (mi >> 1);
            const uint32_t lE = cb + rr * 16 + (hx & 1) * PL + (hx >> 1) * 16;
            const uint32_t lG = lE + (mi & 2) * 520;
            const int hy = (mi & 1) + (mi >> 1) - 1;
            const uint32_t lA = cb + rr * 16 + (hy & 1) * PL + (hy >> 1) * 16;
            const uint32_t ma = cb + C_BP + (mi & 1) * RPL + (mi >> 1) * 128 + rr * 16;
            uint32_t acc[12][2];
#pragma unroll
            for (int i = 0; i < 12; i++) acc[i][0] = acc[i][1] = 0;
            auto group = [&](auto G) {
#pragma unroll
                for (int h = 4 * G.value; h < 4 * G.value + 4; h++) {
                    uint32_t qe[4], qf[4], qg[4], qz[2];
                    ldsm4t(qe, lA + 128 * h + C_A3); ldsm4t(qf, lE + 128 * h + C_W5);
                    if (h < 8) { ldsm4t(qg, lG + 128 * h + C_W7); ldsm2t(qz, lE + 128 * h + C_Z5); }
#pragma unroll
                    for (int i = 0; i < 5; i++)
                        if (h + i < 12) mma_hh(acc[h + i], qe, B2[i][0], B2[i][1]);
#pragma unroll
                    for (int i = 0; i < 5; i++)
                        if (h + i < 12) mma_hh(acc[h + i], qf, B2[i][2], B2[i][3]);
#pragma unroll
                    for (int i = 11; i >= 4; i--)
                        if (h + i < 12) mma_hh(acc[h + i], qg, B3[i - 4][0], B3[i - 4][1]);
                    if (h < 8) mma_h8(acc[h + 4], qz[0], qz[1], bz);
                }
                constexpr int o = 4 * G.value;
                stsm4t(ma + 128 * o, acc[o][0], acc[o][1], acc[o + 1][0], acc[o + 1][1]);
                stsm4t(ma + 128 * o + 256, acc[o + 2][0], acc[o + 2][1], acc[o + 3][0], acc[o + 3][1]);
            };
            bar_sync(0, 256);  TS(12); group(std::integral_constant<int, 0>{}); bar_arrive(1, ALT ? 256 : 384); TS(9);
            uint4* pp = (uint4*)(sc->acc + g * 1024 + cl * 16 + 2 * t);
            uint4 wq = make_uint4(0, 0, 0, 0);
            uint32_t rkey = 0;
            if (ch == 0) {
                flag_wait(sb + OFF_RK + 32, 1);
                rkey = lds32(sb + OFF_RK + 36);
                if (((~rkey >> 7) & 1) == (uint32_t)rk) wq = ld_relaxed4(pp);
            }
            bar_sync(6, 256);  TS(13); group(std::integral_constant<int, 1>{}); bar_arrive(2, ALT ? 256 : 384); TS(10);
            bar_sync(9, 256); TS(14); group(std::integral_constant<int, 2>{}); bar_arrive(3, ALT ? 256 : 384); TS(11);
            if (ch == 0) {
                const uint32_t rrow = ~rkey & 2047u;
                if (((rrow >> 7) & 1) == (uint32_t)rk) {
                    const uint32_t c = 2 * t, jt = rrow >> 8;
                    const uint32_t xr = __ldg((const uint32_t*)((const uint16_t*)x + rrow * 512 + 8 * cl + c));
                    TS(16);
#pragma unroll 1
                    for (int n = 0; n < SPIN_LIMIT; n++) {
                        const uint32_t cnt = g < (NFFN & 7) ? NFFN / 8 + 1 : NFFN / 8;
                        if (__all_sync(~0u, (wq.x & 255u) == cnt && (wq.z & 255u) == cnt)) break;
                        __nanosleep(FSLEEP);
                        wq = ld_relaxed4(pp);
                    }
                    TS(17);
                    *pp = make_uint4(0, 0, 0, 0);
                    float e0 = __ll2float_rn((long long)(((uint64_t)wq.y << 32) | wq.x)) * (1.f / 268435456.f);
                    float e1 = __ll2float_rn((long long)(((uint64_t)wq.w << 32) | wq.z)) * (1.f / 268435456.f);
#pragma unroll
                    for (int o = 4; o < 32; o <<= 1) { e0 += __shfl_xor_sync(~0u, e0, o); e1 += __shfl_xor_sync(~0u, e1, o); }
                    const uint32_t xn = lds32(sb + OFF_XN + (cl & 31) * 32 + (cl >> 5) * 16 + c * 2);
                    const float rsel = sigmoidf_(__uint_as_float((rkey ^ (uint32_t)((int32_t)~rkey >> 31 | 0x80000000)) & 0xffff0000u));
                    const uint32_t bo = badd2(xn, bmul2(packbf(e0, e1), packbf(rsel, rsel)));
                    const uint32_t gate = packbf(siluf_(bflo(bo)), siluf_(bfhi(bo)));
                    flag_wait(sb + OFF_FLG + 64 + jt * 4, 1);
                    const uint32_t yy = sb + OFF_Y + jt * 2048 + c * 128 + (rrow & 126) * 2;
                    const uint32_t y = __byte_perm(lds32(yy), lds32(yy + 1024), (rrow & 1) ? 0x7632 : 0x5410);
                    if (lane < 4) *(uint32_t*)(out + rrow * 512 + 8 * cl + c) = badd2(xr, bmul2(y, gate));
                    TS(18);
                }
            }
            }
            TS(5);
        }
    } else {
        asm volatile("setmaxnreg.dec.sync.aligned.u32 72;");
        LANEVARS
        const uint32_t xs = sb + OFF_XS + j * 2048 + lane * 16;
        uint32_t gt[16];
        const uint32_t yt = sb + OFF_Y + j * 2048;
        const uint32_t ua = sb + OFF_U + 128 + s * 128 + (lane & 2) * (UPL / 2) + g * 16 + (lane & 1) * 8;
        const uint32_t ur = mapa(ua, rk ^ 1), um = mapa(bars + (BAR_U + s) * 8, rk ^ 1);
        mbar_wait(bars + (BAR_X + j) * 8);
        {
            const uint32_t sl = rk ? 0x7632 : 0x5410, sr = sl ^ 0x2222;
            const uint4 r0 = lds128(xs), r1 = lds128(xs + 512), r2 = lds128(xs + 1024), r3 = lds128(xs + 1536);
            const uint32_t q0[4] = {r0.x, r0.y, r0.z, r0.w}, q1[4] = {r1.x, r1.y, r1.z, r1.w};
            const uint32_t q2[4] = {r2.x, r2.y, r2.z, r2.w}, q3[4] = {r3.x, r3.y, r3.z, r3.w};
#pragma unroll
            for (int c = 0; c < 4; c++) {
                gt[2 * c] = __byte_perm(q0[c], q1[c], sl); gt[8 + 2 * c] = __byte_perm(q0[c], q1[c], sr);
                gt[2 * c + 1] = __byte_perm(q2[c], q3[c], sl); gt[9 + 2 * c] = __byte_perm(q2[c], q3[c], sr);
            }
        }
        const uint4* sp = sc->stats + (cl & (NREP - 1)) * (NCTA * 8) + 64 * s + 8 * g + t;
        uint4 st0 = ld_relaxed4(sp), st1 = ld_relaxed4<64>(sp);
        const uint32_t tag = (ld_relaxed1(sc->epoch + 8 * b + rr) + 1) & 0xffffu;
        const uint32_t tt = tag * 0x10001u;
        TS(18);
#pragma unroll 1
        for (int n = 0; n < SPIN_LIMIT; n++) {
            if (__all_sync(~0u, st0.w == tt && st1.w == tt)) break;
            st0 = ld_relaxed4(sp); st1 = ld_relaxed4<64>(sp);
        }
        TS(4);
        TS(3);
#pragma unroll
        for (int k = 0; k < 8; k++) {
            const int c = (k >> 1) + ((k & 1) ? 0 : 4);
            const uint32_t n0 = norm2(gt[2 * c], st0.x, st0.y, st0.z), n1 = norm2(gt[2 * c + 1], st1.x, st1.y, st1.z);
            gt[2 * c] = packh(bflo(n0), bfhi(n0)); gt[2 * c + 1] = packh(bflo(n1), bfhi(n1));
            if (c < 4) sts64(ua + c * UCH, gt[2 * c], gt[2 * c + 1]);
            else st_async64(ur + (c - 4) * UCH, gt[2 * c], gt[2 * c + 1], um);
        }
        __syncwarp();
        if (lane == 0) asm volatile("mbarrier.arrive.shared::cta.b64 _, [%0];" :: "r"(bars + (BAR_U + s) * 8) : "memory");
        TS(5);
        if (j < 4) flag_wait(sb + OFF_RK + 44, 1);
        if (j < 4) {
#pragma unroll 1
            for (int po = 0; po < 1536; po += 512) {
                windows(sb, ch, po);
                bar_arrive(po < 512 ? 0 : po < 1024 ? 6 : 9, 256);
            }
        }
        uint32_t rkey = 0;
        uint4 xv, xb, sv;
        if (j == RJ) {
            uint32_t rv[4];
#pragma unroll 1
            for (int n = 0; n < SPIN_LIMIT; n++) {
#pragma unroll
                for (int i = 0; i < 4; i++) rv[i] = ld_relaxed1(sc->route + 8 * lane + 256 * i);
                const uint32_t tg = tag << 11;
                const uint32_t bad = ((rv[0] ^ tg) | (rv[1] ^ tg) | (rv[2] ^ tg) | (rv[3] ^ tg)) & 0xf800u;
                if (__all_sync(~0u, bad == 0)) break;
            }
            rkey = __reduce_max_sync(~0u, max(max(rv[0], rv[1]), max(rv[2], rv[3])));
            const uint32_t rrow = ~rkey & 2047u;
            TS(10);
            xv = ld_relaxed4(x + rrow * 64 + lane); xb = ld_relaxed4<512>(x + rrow * 64 + lane);
            sv = ld_relaxed4(sc->stats + (cl & (NREP - 1)) * (NCTA * 8) + stat_slot(rrow));
            if (elect_one()) load_w();
            __syncwarp();
        }
        TS(6);
#pragma unroll 1
        for (int i = 0; i < 2; i++) {
            uint32_t q[8];
#pragma unroll
            for (int k = 0; k < 8; k++) {
                const __half2 hh = __hmul2(*reinterpret_cast<__half2*>(&gt[k]), __float2half2_rn(0.5f));
                const float lo = __low2float(hh), hi = __high2float(hh);
                float tl, th;
                asm("tanh.approx.f32 %0, %1;" : "=f"(tl) : "f"(lo));
                asm("tanh.approx.f32 %0, %1;" : "=f"(th) : "f"(hi));
                q[k] = packbf(fmaf(lo, tl, lo), fmaf(hi, th, hi));
            }
#pragma unroll
            for (int k = 0; k < 8; k++) { gt[k] = gt[k + 8]; gt[k + 8] = q[k]; }
        }
        TS(16);
        if (j == RJ) {
#pragma unroll 1
            for (int n = 0; n < SPIN_LIMIT && sv.w != tt; n++) sv = ld_relaxed4(sc->stats + stat_slot(~rkey & 2047u));
            const uint32_t sel = (rkey & 1) ? 0x1010 : 0x3232;
            const uint32_t m2 = __byte_perm(sv.x, 0, sel), h2 = __byte_perm(sv.y, 0, sel), l2 = __byte_perm(sv.z, 0, sel);
            sts128(sb + OFF_XN + lane * 32, norm2(xv.x, m2, h2, l2), norm2(xv.y, m2, h2, l2), norm2(xv.z, m2, h2, l2), norm2(xv.w, m2, h2, l2));
            sts128(sb + OFF_XN + lane * 32 + 16, norm2(xb.x, m2, h2, l2), norm2(xb.y, m2, h2, l2), norm2(xb.z, m2, h2, l2), norm2(xb.w, m2, h2, l2));
            sts32(sb + OFF_RK + 36, rkey);
            asm volatile("fence.proxy.async.shared::cta;" ::: "memory");
            __syncwarp();
            st_flag(sb + OFF_RK + 32, 1);
            TS(11);
        }
        if (j >= 4 && b < NFFN) {
            flag_wait(sb + OFF_RK + 32, 1);
            mbar_wait_long(bars + BAR_W * 8);
            TS(12);
            float d[8][4];
            const uint64_t da = mkdesc(sb + OFF_WG, 8192, 256, 3), db = mkdesc(sb + OFF_XN, 32, 128, 0);
            d[0][0] = d[0][1] = d[0][2] = d[0][3] = 0.f;
            asm volatile("wgmma.fence.sync.aligned;" ::: "memory");
#pragma unroll
            for (int k = 0; k < 16; k++) wgmma8<1>(d[0], da + 32 * k, db + 4 * k);
            asm volatile("wgmma.commit_group.sync.aligned;" ::: "memory");
            asm volatile("wgmma.wait_group.sync.aligned 0;" ::: "memory");
            asm volatile("" : "+f"(d[0][0]), "+f"(d[0][1]), "+f"(d[0][2]), "+f"(d[0][3]));
            if (t == 0) {
                sts32f(sb + OFF_FP + g * 16 + ch * 4, (ch & 1) ? d[0][1] : d[0][0]);
                sts32f(sb + OFF_FP + g * 16 + ch * 4 + 128, (ch & 1) ? d[0][3] : d[0][2]);
            }
            bar_sync(7, 128);
            {
                const float4 p0 = lds128f(sb + OFF_FP + rr * 32), p1 = lds128f(sb + OFF_FP + rr * 32 + 16);
                const float g0 = rbf(p0.x + p0.y), g1 = rbf(p1.x + p1.y);
                const uint32_t hp = bmul2(packbf(siluf_(g0), siluf_(g1)), packbf(p0.z + p0.w, p1.z + p1.w));
                sts32(sb + OFF_FP + 256 + (rr >> 2) * 128 + mi * 32 + (rr & 3) * 4, hp);
            }
            asm volatile("fence.proxy.async.shared::cta;" ::: "memory");
            bar_sync(7, 128);
            const uint64_t dd = mkdesc(sb + OFF_WD, 1024, 1024, 1), dh = mkdesc(sb + OFF_FP + 256, 128, 128, 0);
            asm volatile("wgmma.fence.sync.aligned;" ::: "memory");
#pragma unroll
            for (int i = 0; i < 8; i++)
                asm volatile("wgmma.mma_async.sync.aligned.m64n8k16.f32.bf16.bf16 {%0,%1,%2,%3}, %4, %5, 0, 1, 1, 1, 0;"
                             : "=f"(d[i][0]), "=f"(d[i][1]), "=f"(d[i][2]), "=f"(d[i][3]) : "l"(dd + 128 * i), "l"(dh));
            asm volatile("wgmma.commit_group.sync.aligned;" ::: "memory");
            asm volatile("wgmma.wait_group.sync.aligned 0;" ::: "memory");
            const bool t1 = t & 1, t2 = t & 2;
            long long* gp = sc->acc + (b & 7) * 1024 + ((t >> 1) * 8 + 2 * ch + (t & 1)) * 16 + g;
#pragma unroll
            for (int k = 0; k < 4; k++) {
                asm volatile("" : "+f"(d[2 * k][0]), "+f"(d[2 * k][2]), "+f"(d[2 * k + 1][0]), "+f"(d[2 * k + 1][2]));
                const float v = t2 ? (t1 ? d[2 * k + 1][2] : d[2 * k + 1][0]) : (t1 ? d[2 * k][2] : d[2 * k][0]);
                asm volatile("red.relaxed.gpu.global.add.u64 [%0], %1;" :: "l"(gp + 256 * k),
                             "l"((__float2ll_rn(v * 268435456.f) & ~255LL) + 1) : "memory");
            }
            TS(13);
        }
        {
            flag_wait(sb + OFF_RK + 32, 1);
            const uint32_t yl = yt + rk * 1024 + lane * 8, yr = yt + (rk ^ 1) * 1024 + lane * 8, se = rk ? 0x1054 : 0x5410, so = se ^ 0x2222;
            mbar_wait_long(bars + (BAR_Y + j) * 8);
            TS(7);
#pragma unroll
            for (int c = 0; c < 8; c++) {
                const uint2 y = lds64((c < 4 ? yl : yr) + (c & 3) * 256);
                gt[2 * c] = bmul2(y.x, gt[2 * c]); gt[2 * c + 1] = bmul2(y.y, gt[2 * c + 1]);
            }
#pragma unroll
            for (int r = 0; r < 4; r++) {
                const uint32_t sel = (r & 1) ? so : se;
                const int o = r >> 1;
                sts128(xs + r * 512, __byte_perm(gt[o], gt[8 + o], sel), __byte_perm(gt[2 + o], gt[10 + o], sel),
                       __byte_perm(gt[4 + o], gt[12 + o], sel), __byte_perm(gt[6 + o], gt[14 + o], sel));
            }
            asm volatile("fence.proxy.async.shared::cta;" ::: "memory");
            __syncwarp();
            if (j == 7) sc->epoch[8 * b + rr] = tag;
            if (elect_one()) {
                asm volatile("cp.reduce.async.bulk.tensor.3d.global.shared::cta.add.bulk_group [%0, {%2, %3, %4}], [%1];"
                             :: "l"(&tm.o), "r"(sb + OFF_XS + j * 2048), "r"(cl * 8), "r"(s * 32), "r"(0) : "memory");
                asm volatile("cp.async.bulk.commit_group;" ::: "memory");
                TS(8);
                asm volatile("cp.async.bulk.wait_group 0;" ::: "memory");
                st_flag(sb + OFF_FLG + 64 + j * 4, 1);
            }
            __syncwarp();
        }
        TS(9);
    }
    TS_DUMP
}

typedef CUresult (*EncodeFn)(CUtensorMap*, CUtensorMapDataType, cuuint32_t, void*, const cuuint64_t*, const cuuint64_t*,
                             const cuuint32_t*, const cuuint32_t*, CUtensorMapInterleave, CUtensorMapSwizzle,
                             CUtensorMapL2promotion, CUtensorMapFloatOOBfill);

}

extern "C" void kernel_launch(void* const* d_in, const int* in_sizes, int n_in, void* d_out, int out_size) {
    static Maps tm;
    static Scratch* sc = nullptr;
    static void* key[5] = {nullptr, nullptr, nullptr, nullptr, nullptr};
    if (key[0] != d_in[0] || key[1] != d_out || key[2] != d_in[9] || key[3] != d_in[10] || key[4] != d_in[11]) {
        void* fn = nullptr;
        cudaDriverEntryPointQueryResult qr;
        cudaGetDriverEntryPoint("cuTensorMapEncodeTiled", &fn, cudaEnableDefault, &qr);
        EncodeFn enc = (EncodeFn)fn;
        const cuuint32_t es[4] = {1, 1, 1, 1};
        auto make = [&](CUtensorMap* m, void* p, cuuint64_t d0, cuuint64_t d1, cuuint64_t d2, cuuint64_t s1, cuuint64_t s2,
                        cuuint32_t b0, cuuint32_t b1, cuuint32_t b2, CUtensorMapSwizzle sw) {
            const cuuint64_t gd[3] = {d0, d1, d2}, gs[2] = {s1, s2};
            const cuuint32_t bd[3] = {b0, b1, b2};
            enc(m, CU_TENSOR_MAP_DATA_TYPE_BFLOAT16, 3, p, gd, gs, bd, es, CU_TENSOR_MAP_INTERLEAVE_NONE, sw,
                CU_TENSOR_MAP_L2_PROMOTION_NONE, CU_TENSOR_MAP_FLOAT_OOB_FILL_NONE);
        };
        make(&tm.x, d_in[0], 512, 512, 4, 4096, 1024, 8, 32, 4, CU_TENSOR_MAP_SWIZZLE_NONE);
        make(&tm.o, d_out, 512, 512, 4, 4096, 1024, 8, 32, 4, CU_TENSOR_MAP_SWIZZLE_NONE);
        make(&tm.w[0], d_in[9], 1376, 256, 2, 2752, 256 * 2752, 16, 256, 2, CU_TENSOR_MAP_SWIZZLE_32B);
        make(&tm.w[1], d_in[10], 1376, 256, 2, 2752, 256 * 2752, 16, 256, 2, CU_TENSOR_MAP_SWIZZLE_32B);
        make(&tm.w[2], d_in[11], 64, 1376, 8, 1024, 128, 64, 16, 8, CU_TENSOR_MAP_SWIZZLE_128B);
        for (int i = 0; i < 3; i++) tm.wp[i] = (const char*)d_in[9 + i];
        cudaGetSymbolAddress((void**)&sc, g_scratch);
        cudaFuncSetAttribute(fused_kernel, cudaFuncAttributeMaxDynamicSharedMemorySize, SMEM_BYTES + TS_SMEM + GT_SMEM);
        key[0] = d_in[0]; key[1] = d_out; key[2] = d_in[9]; key[3] = d_in[10]; key[4] = d_in[11];
    }
    fused_kernel<<<NCTA, 640, SMEM_BYTES + TS_SMEM + GT_SMEM>>>(
        (const uint2*)d_in[1], (const uint2*)d_in[2], (const uint2*)d_in[3],
        (const uint2*)d_in[4], (const uint16_t*)d_in[5], (const uint16_t*)d_in[6], (const uint4*)d_in[0], sc, (const uint4*)d_in[8],
        (uint16_t*)d_out, tm);
}
```
